```python
import torch

def _softmax(x, axis=-1):
    return torch.softmax(x, dim=axis)
def _gelu(x):
    return torch.nn.functional.gelu(x, approximate="tanh")
def _silu(x):
    return torch.nn.functional.silu(x)
def _sigmoid(x):
    return torch.sigmoid(x)
def _layernorm(x, axis=-1, eps=1e-5):
    m = x.mean(dim=axis, keepdim=True)
    v = x.var(dim=axis, keepdim=True, unbiased=False)
    return (x - m) / torch.sqrt(v + eps)
def _scatter_add(tgt, idx, src, axis=0):
    return tgt.clone().index_add_(axis, idx, src)
def _segment_sum(src, seg, n):
    out = torch.zeros((n,) + src.shape[1:], dtype=src.dtype)
    return out.index_add_(0, seg, src)
def _pad(x, pw):
    flat = tuple(v for pair in reversed(pw) for v in pair)
    return torch.nn.functional.pad(x, flat)

kernel_name = 'concat_heads__softmax_full_mha__linear_attn_block__prompt'

def setup_inputs():

    _w = (lambda a: (lambda t: t.to(torch.bfloat16) if t.is_floating_point() else t)(torch.as_tensor(a)))
    def _A_setup():
        B, S, D = 1, 2048, 448
        return {
            "x": _w((lambda *s: torch.randn(*s, dtype=torch.bfloat16) * 0.2)(B, S, D)),
            "wqkv": _w((lambda *s: torch.randn(*s, dtype=torch.bfloat16) * 0.2)(D, 3 * D)),
            "wo": _w((lambda *s: torch.randn(*s, dtype=torch.bfloat16) * 0.05)(D, D)),
        }
    _A_in = _A_setup()

    def _B_setup():
        B, S, D = 1, 2048, 448
        return {
            "x": _w((lambda *s: torch.randn(*s, dtype=torch.bfloat16) * 0.05)(B, S, D)),
            "wqkv": _w((lambda *s: torch.randn(*s, dtype=torch.bfloat16) * 1.6)(D, 3 * D)),
            "wo": _w((lambda *s: torch.randn(*s, dtype=torch.bfloat16) * 0.05)(D, D)),
        }
    _B_in = _B_setup()

    return {
        "A_x": _A_in["x"],
        "A_wqkv": _A_in["wqkv"],
        "A_wo": _A_in["wo"],
        "B_x": _B_in["x"],
        "B_wqkv": _B_in["wqkv"],
        "B_wo": _B_in["wo"],
    }

def reference(A_x, A_wqkv, A_wo, B_x, B_wqkv, B_wo):
    def _A_ref(x, wqkv, wo):
        B, S, D = x.shape
        H = 16; Dh = D // H
        qkv = (lambda x, *d: x.permute(*d))((x @ wqkv).reshape(B, S, 3, H, Dh), 2, 0, 3, 1, 4)
        q, k, v = qkv[0], qkv[1], qkv[2]
        scale = Dh ** -0.5
        scores = torch.einsum("bhqd,bhkd->bhqk", q, k) * scale
        p = _softmax(scores, axis=-1)
        o = torch.einsum("bhqk,bhkd->bhqd", p, v)
        return (lambda x, *d: x.permute(*d))(o, 0, 2, 1, 3).reshape(B, S, D) @ wo

    def _B_ref(x, wqkv, wo):
        B, S, D = x.shape
        H = 16; Dh = D // H
        qkv = (lambda x, *d: x.permute(*d))((x @ wqkv).reshape(B, S, 3, H, Dh), 2, 0, 3, 1, 4)
        q, k, v = qkv[0], qkv[1], qkv[2]
        phi = lambda t: torch.where(t > 0, t + 1, torch.exp(t)) + 1e-6
        pq, pk = phi(q), phi(k)
        kv = torch.einsum("bhsd,bhse->bhde", pk, v)
        z = torch.einsum("bhsd->bhd", pk)
        num = torch.einsum("bhqd,bhde->bhqe", pq, kv)
        den = torch.einsum("bhqd,bhd->bhq", pq, z)[..., None] + 1e-6
        o = num / den
        return (lambda x, *d: x.permute(*d))(o, 0, 2, 1, 3).reshape(B, S, D) @ wo

    a = _A_ref(A_x, A_wqkv, A_wo)
    b = _B_ref(B_x, B_wqkv, B_wo)
    return torch.concatenate([a, b], axis=-1)
```

```cpp
#include <cuda_runtime.h>
#include <cuda.h>
#include <cuda_bf16.h>
#include <cuda_fp16.h>
#include <stdint.h>

namespace {

#define PMASK 0xB3B3
#define EPV 4
#define KVWG 0
#define MIDIT0 5
#define MIDIT1 5
constexpr int KVIT = 1, MIDWG0 = 2, MIDWG1 = 3;
#define NPRO 2
#define NB1 3
#define ASTART 12
#define NSLOT 4
#define XFIRST 0
#define LOOK NSLOT
#define LOOKN 11
#define PROMO CU_TENSOR_MAP_L2_PROMOTION_L2_128B
#define AORD 2
#define HPORD 0x76543210u

constexpr int NWORK = 128, NCTA = 132, NTHREADS = 640;
constexpr uint32_t UNIT = 16384;
constexpr uint32_t SM_BAR = 14 * UNIT;
enum { B_FULL = 0, B_Q = 14, B_G = 15, B_KP = 16, B_WO = 24, B_O = 32, B_Z = 46, B_ACK = 47, B_D = 48, B_QR = 57, B_BD = 58, B_LI = 59, B_PAIR = 60, B_EM = 64, B_FW = 80 };
constexpr uint32_t SM_KN = SM_BAR + 8 * 96;
constexpr uint32_t SM_KG = SM_KN + 96;
constexpr uint32_t SM_QN = SM_KG + 32;
constexpr uint32_t SMEM_BYTES = SM_BAR + 1024;
constexpr uint32_t PAIR_UNIT = 0x64A0864Au;
constexpr uint32_t WO_UNIT = 0x41098D2u;
constexpr uint64_t O_HALF0 = 0x15141716180706ull;
constexpr uint64_t O_HALF1 = 0x190F0E0D0C0B0Aull;
__device__ __forceinline__ int ring(int n) { return NSLOT == 4 ? n & 3 : n >= 10 ? n - 10 : n >= 5 ? n - 5 : n; }
__device__ __forceinline__ uint32_t x_off(int n) { return (ring(n) == 4 ? 10 : ring(n)) * UNIT; }
__device__ __forceinline__ uint32_t w_off(int n) { return ring(n) == 4 ? 11 * UNIT : 4 * UNIT + ring(n) * 24576; }
__device__ __forceinline__ uint32_t pair_off(int i) { return ((PAIR_UNIT >> (4 * (i & 7))) & 15) * UNIT; }
__device__ __forceinline__ int kp_bar(int i) { return B_KP + (i < 2 ? i ^ 1 : i); }
__device__ __forceinline__ uint32_t wo_off(int k) { return ((WO_UNIT >> (4 * k)) & 15) * UNIT; }
__device__ __forceinline__ uint32_t o_off(int w, int k) { return (uint32_t)(((w ? O_HALF1 : O_HALF0) >> (8 * k)) & 255) * (UNIT / 2); }

enum { F_A = 0, F_B = 16 * 32, F_Z = 24 * 32, F_O = 32 * 32, F_EPOCH = 64 * 32, F_TOTAL = F_EPOCH + 132 * 8 };

struct __align__(1024) Scratch {
    uint4 KV[16 * 2048 * 8];
    uint4 O[2 * 32 * 7 * 512];
    float4 KVP[8 * 16 * 4 * 128];
    uint32_t KVZ[8 * 2048];
    unsigned flag[F_TOTAL];
};
__device__ Scratch g_scratch;

struct Params {
    Scratch* s;
    const uint8_t* in[2];
    uint8_t* out_ptr;
    CUtensorMap x[2], w[2], wo64[2], wo48[2];
};
#define g_KV (P.s->KV)
#define g_O (P.s->O)
#define g_KVP (P.s->KVP)
#define g_KVZ (P.s->KVZ)
#define g_flag (P.s->flag)

__device__ __forceinline__ void mma_bf16_ss_n64_tt(float (&d)[32], uint64_t da, uint64_t db, int acc) {
    asm volatile("{\n.reg .pred p;\nsetp.ne.b32 p, %34, 0;\n"
        "wgmma.mma_async.sync.aligned.m64n64k16.f32.bf16.bf16 "
        "{%0,%1,%2,%3,%4,%5,%6,%7,%8,%9,%10,%11,%12,%13,%14,%15,%16,%17,%18,%19,%20,%21,%22,%23,%24,%25,%26,%27,%28,%29,%30,%31}, "
        "%32, %33, p, 1, 1, 1, 1;\n}\n"
        : "+f"(d[0]), "+f"(d[1]), "+f"(d[2]), "+f"(d[3]), "+f"(d[4]), "+f"(d[5]), "+f"(d[6]), "+f"(d[7]),
          "+f"(d[8]), "+f"(d[9]), "+f"(d[10]), "+f"(d[11]), "+f"(d[12]), "+f"(d[13]), "+f"(d[14]), "+f"(d[15]),
          "+f"(d[16]), "+f"(d[17]), "+f"(d[18]), "+f"(d[19]), "+f"(d[20]), "+f"(d[21]), "+f"(d[22]), "+f"(d[23]),
          "+f"(d[24]), "+f"(d[25]), "+f"(d[26]), "+f"(d[27]), "+f"(d[28]), "+f"(d[29]), "+f"(d[30]), "+f"(d[31])
        : "l"(da), "l"(db), "r"(acc));
}
__device__ __forceinline__ void mma_bf16_ss_n64(float (&d)[32], uint64_t da, uint64_t db, int acc) {
    asm volatile("{\n.reg .pred p;\nsetp.ne.b32 p, %34, 0;\n"
        "wgmma.mma_async.sync.aligned.m64n64k16.f32.bf16.bf16 "
        "{%0,%1,%2,%3,%4,%5,%6,%7,%8,%9,%10,%11,%12,%13,%14,%15,%16,%17,%18,%19,%20,%21,%22,%23,%24,%25,%26,%27,%28,%29,%30,%31}, "
        "%32, %33, p, 1, 1, 0, 1;\n}\n"
        : "+f"(d[0]), "+f"(d[1]), "+f"(d[2]), "+f"(d[3]), "+f"(d[4]), "+f"(d[5]), "+f"(d[6]), "+f"(d[7]),
          "+f"(d[8]), "+f"(d[9]), "+f"(d[10]), "+f"(d[11]), "+f"(d[12]), "+f"(d[13]), "+f"(d[14]), "+f"(d[15]),
          "+f"(d[16]), "+f"(d[17]), "+f"(d[18]), "+f"(d[19]), "+f"(d[20]), "+f"(d[21]), "+f"(d[22]), "+f"(d[23]),
          "+f"(d[24]), "+f"(d[25]), "+f"(d[26]), "+f"(d[27]), "+f"(d[28]), "+f"(d[29]), "+f"(d[30]), "+f"(d[31])
        : "l"(da), "l"(db), "r"(acc));
}
__device__ __forceinline__ void mma_bf16_ss_n120(float (&d)[60], uint64_t da, uint64_t db, int acc) {
    asm volatile("{\n.reg .pred p;\nsetp.ne.b32 p, %62, 0;\n"
        "wgmma.mma_async.sync.aligned.m64n120k16.f32.bf16.bf16 "
        "{%0,%1,%2,%3,%4,%5,%6,%7,%8,%9,%10,%11,%12,%13,%14,%15,%16,%17,%18,%19,%20,%21,%22,%23,%24,%25,%26,%27,%28,%29,%30,%31,%32,%33,%34,%35,%36,%37,%38,%39,%40,%41,%42,%43,%44,%45,%46,%47,%48,%49,%50,%51,%52,%53,%54,%55,%56,%57,%58,%59}, "
        "%60, %61, p, 1, 1, 0, 1;\n}\n"
        : "+f"(d[0]), "+f"(d[1]), "+f"(d[2]), "+f"(d[3]), "+f"(d[4]), "+f"(d[5]), "+f"(d[6]), "+f"(d[7]),
          "+f"(d[8]), "+f"(d[9]), "+f"(d[10]), "+f"(d[11]), "+f"(d[12]), "+f"(d[13]), "+f"(d[14]), "+f"(d[15]),
          "+f"(d[16]), "+f"(d[17]), "+f"(d[18]), "+f"(d[19]), "+f"(d[20]), "+f"(d[21]), "+f"(d[22]), "+f"(d[23]),
          "+f"(d[24]), "+f"(d[25]), "+f"(d[26]), "+f"(d[27]), "+f"(d[28]), "+f"(d[29]), "+f"(d[30]), "+f"(d[31]),
          "+f"(d[32]), "+f"(d[33]), "+f"(d[34]), "+f"(d[35]), "+f"(d[36]), "+f"(d[37]), "+f"(d[38]), "+f"(d[39]),
          "+f"(d[40]), "+f"(d[41]), "+f"(d[42]), "+f"(d[43]), "+f"(d[44]), "+f"(d[45]), "+f"(d[46]), "+f"(d[47]),
          "+f"(d[48]), "+f"(d[49]), "+f"(d[50]), "+f"(d[51]), "+f"(d[52]), "+f"(d[53]), "+f"(d[54]), "+f"(d[55]),
          "+f"(d[56]), "+f"(d[57]), "+f"(d[58]), "+f"(d[59])
        : "l"(da), "l"(db), "r"(acc));
}
__device__ __forceinline__ void mma_bf16_ss_n48(float (&d)[24], uint64_t da, uint64_t db, int acc) {
    asm volatile("{\n.reg .pred p;\nsetp.ne.b32 p, %26, 0;\n"
        "wgmma.mma_async.sync.aligned.m64n48k16.f32.bf16.bf16 "
        "{%0,%1,%2,%3,%4,%5,%6,%7,%8,%9,%10,%11,%12,%13,%14,%15,%16,%17,%18,%19,%20,%21,%22,%23}, "
        "%24, %25, p, 1, 1, 0, 1;\n}\n"
        : "+f"(d[0]), "+f"(d[1]), "+f"(d[2]), "+f"(d[3]), "+f"(d[4]), "+f"(d[5]), "+f"(d[6]), "+f"(d[7]),
          "+f"(d[8]), "+f"(d[9]), "+f"(d[10]), "+f"(d[11]), "+f"(d[12]), "+f"(d[13]), "+f"(d[14]), "+f"(d[15]),
          "+f"(d[16]), "+f"(d[17]), "+f"(d[18]), "+f"(d[19]), "+f"(d[20]), "+f"(d[21]), "+f"(d[22]), "+f"(d[23])
        : "l"(da), "l"(db), "r"(acc));
}
__device__ __forceinline__ void mma_bf16_ss_n112(float (&d)[56], uint64_t da, uint64_t db, int acc) {
    asm volatile("{\n.reg .pred p;\nsetp.ne.b32 p, %58, 0;\n"
        "wgmma.mma_async.sync.aligned.m64n112k16.f32.bf16.bf16 "
        "{%0,%1,%2,%3,%4,%5,%6,%7,%8,%9,%10,%11,%12,%13,%14,%15,%16,%17,%18,%19,%20,%21,%22,%23,%24,%25,%26,%27,%28,%29,%30,%31,%32,%33,%34,%35,%36,%37,%38,%39,%40,%41,%42,%43,%44,%45,%46,%47,%48,%49,%50,%51,%52,%53,%54,%55}, "
        "%56, %57, p, 1, 1, 0, 1;\n}\n"
        : "+f"(d[0]), "+f"(d[1]), "+f"(d[2]), "+f"(d[3]), "+f"(d[4]), "+f"(d[5]), "+f"(d[6]), "+f"(d[7]),
          "+f"(d[8]), "+f"(d[9]), "+f"(d[10]), "+f"(d[11]), "+f"(d[12]), "+f"(d[13]), "+f"(d[14]), "+f"(d[15]),
          "+f"(d[16]), "+f"(d[17]), "+f"(d[18]), "+f"(d[19]), "+f"(d[20]), "+f"(d[21]), "+f"(d[22]), "+f"(d[23]),
          "+f"(d[24]), "+f"(d[25]), "+f"(d[26]), "+f"(d[27]), "+f"(d[28]), "+f"(d[29]), "+f"(d[30]), "+f"(d[31]),
          "+f"(d[32]), "+f"(d[33]), "+f"(d[34]), "+f"(d[35]), "+f"(d[36]), "+f"(d[37]), "+f"(d[38]), "+f"(d[39]),
          "+f"(d[40]), "+f"(d[41]), "+f"(d[42]), "+f"(d[43]), "+f"(d[44]), "+f"(d[45]), "+f"(d[46]), "+f"(d[47]),
          "+f"(d[48]), "+f"(d[49]), "+f"(d[50]), "+f"(d[51]), "+f"(d[52]), "+f"(d[53]), "+f"(d[54]), "+f"(d[55])
        : "l"(da), "l"(db), "r"(acc));
}
__device__ __forceinline__ void mma_qk_h128(uint32_t (&d)[32], uint32_t a0, uint32_t a1, uint32_t a2, uint32_t a3, uint64_t db, int acc) {
    asm volatile("{\n.reg .pred p;\nsetp.ne.b32 p, %37, 0;\n"
        "wgmma.mma_async.sync.aligned.m64n128k16.f16.f16.f16 "
        "{%0,%1,%2,%3,%4,%5,%6,%7,%8,%9,%10,%11,%12,%13,%14,%15,%16,%17,%18,%19,%20,%21,%22,%23,%24,%25,%26,%27,%28,%29,%30,%31}, "
        "{%32,%33,%34,%35}, %36, p, 1, 1, 0;\n}\n"
        : "+r"(d[0]), "+r"(d[1]), "+r"(d[2]), "+r"(d[3]), "+r"(d[4]), "+r"(d[5]), "+r"(d[6]), "+r"(d[7]),
          "+r"(d[8]), "+r"(d[9]), "+r"(d[10]), "+r"(d[11]), "+r"(d[12]), "+r"(d[13]), "+r"(d[14]), "+r"(d[15]),
          "+r"(d[16]), "+r"(d[17]), "+r"(d[18]), "+r"(d[19]), "+r"(d[20]), "+r"(d[21]), "+r"(d[22]), "+r"(d[23]),
          "+r"(d[24]), "+r"(d[25]), "+r"(d[26]), "+r"(d[27]), "+r"(d[28]), "+r"(d[29]), "+r"(d[30]), "+r"(d[31])
        : "r"(a0), "r"(a1), "r"(a2), "r"(a3), "l"(db), "r"(acc));
}
__device__ __forceinline__ void mma_pv_h32(uint32_t (&d)[8], uint32_t a0, uint32_t a1, uint32_t a2, uint32_t a3, uint64_t db, int acc) {
    asm volatile("{\n.reg .pred p;\nsetp.ne.b32 p, %13, 0;\n"
        "wgmma.mma_async.sync.aligned.m64n32k16.f16.f16.f16 "
        "{%0,%1,%2,%3,%4,%5,%6,%7}, "
        "{%8,%9,%10,%11}, %12, p, 1, 1, 1;\n}\n"
        : "+r"(d[0]), "+r"(d[1]), "+r"(d[2]), "+r"(d[3]), "+r"(d[4]), "+r"(d[5]), "+r"(d[6]), "+r"(d[7])
        : "r"(a0), "r"(a1), "r"(a2), "r"(a3), "l"(db), "r"(acc));
}

#define WG_FENCE() asm volatile("wgmma.fence.sync.aligned;" ::: "memory")
#define WG_COMMIT() asm volatile("wgmma.commit_group.sync.aligned;" ::: "memory")
#define WG_WAIT(n) asm volatile("wgmma.wait_group.sync.aligned %0;" ::"n"(n) : "memory")

template <int N> __device__ __forceinline__ void pin(float (&a)[N]) {
#pragma unroll
    for (int i = 0; i < N; i++) asm volatile("" : "+f"(a[i])::"memory");
}
template <int N> __device__ __forceinline__ void pin(uint32_t (&a)[N]) {
#pragma unroll
    for (int i = 0; i < N; i++) asm volatile("" : "+r"(a[i])::"memory");
}
template <int N> __device__ __forceinline__ void zero(float (&a)[N]) {
#pragma unroll
    for (int i = 0; i < N; i++) a[i] = 0.f;
    pin(a);
}
template <int N> __device__ __forceinline__ void zero(uint32_t (&a)[N]) {
#pragma unroll
    for (int i = 0; i < N; i++) a[i] = 0u;
    pin(a);
}
__device__ __forceinline__ int lane_id() { int l; asm volatile("mov.u32 %0, %%laneid;" : "=r"(l)); return l; }
#define LANES const int lane = lane_id(), g = lane >> 2, q = lane & 3; (void)g; (void)q
__device__ __forceinline__ uint64_t desc128(uint32_t addr, uint32_t lbo = 16) {
    return (uint64_t)(((addr & 0x3FFFF) >> 4) | ((lbo >> 4) << 16)) | ((uint64_t)0x40000040 << 32);
}
__device__ __forceinline__ uint64_t desc_plain(uint32_t addr, uint32_t lbo, uint32_t sbo) {
    return (uint64_t)(((addr & 0x3FFFF) >> 4) | ((lbo >> 4) << 16)) | ((uint64_t)(sbo >> 4) << 32);
}
__device__ __forceinline__ void mbar_init(uint32_t a, uint32_t c) { asm volatile("mbarrier.init.shared::cta.b64 [%0], %1;" ::"r"(a), "r"(c) : "memory"); }
__device__ __forceinline__ void mbar_expect(uint32_t a, uint32_t b) { asm volatile("mbarrier.arrive.expect_tx.shared::cta.b64 _, [%0], %1;" ::"r"(a), "r"(b) : "memory"); }
__device__ __forceinline__ void mbar_arrive(uint32_t a) { asm volatile("mbarrier.arrive.shared::cta.b64 _, [%0];" ::"r"(a) : "memory"); }
__device__ __forceinline__ void mbar_arrive_rank(uint32_t a, uint32_t rank) {
    asm volatile("{.reg .b32 r; mapa.shared::cluster.u32 r, %0, %1; mbarrier.arrive.shared::cluster.b64 _, [r];}" ::"r"(a), "r"(rank) : "memory");
}
__device__ __forceinline__ void mbar_wait(uint32_t a) {
    asm volatile(
        "{\n.reg .pred p;\n.reg .u32 n;\nmov.u32 n, 0;\n"
        "W_LOOP:\nmbarrier.try_wait.parity.shared::cta.b64 p, [%0], 0;\n@p bra W_DONE;\n"
        "add.u32 n, n, 1;\nsetp.lt.u32 p, n, 0x400000;\n@p bra W_LOOP;\ntrap;\nW_DONE:\n}" ::"r"(a) : "memory");
}
__device__ __forceinline__ void tma2d(uint32_t dst, const CUtensorMap* m, int c0, int c1, uint32_t bar) {
    asm volatile("cp.async.bulk.tensor.2d.shared::cluster.global.mbarrier::complete_tx::bytes [%0], [%1, {%3, %4}], [%2];" ::"r"(dst), "l"(m), "r"(bar), "r"(c0), "r"(c1) : "memory");
}
__device__ __forceinline__ void tma3d_mc(uint32_t dst, const CUtensorMap* m, int c0, int c1, int c2, uint32_t bar) {
    asm volatile("cp.async.bulk.tensor.3d.shared::cluster.global.mbarrier::complete_tx::bytes.multicast::cluster [%0], [%1, {%3, %4, %5}], [%2], %6;" ::"r"(dst), "l"(m), "r"(bar), "r"(c0), "r"(c1), "r"(c2), "h"((uint16_t)3) : "memory");
}
__device__ __forceinline__ void bulk_g2s(uint32_t dst, const void* src, uint32_t bytes, uint32_t bar) {
    asm volatile("cp.async.bulk.shared::cluster.global.mbarrier::complete_tx::bytes [%0], [%1], %2, [%3];" ::"r"(dst), "l"(src), "r"(bytes), "r"(bar) : "memory");
}
__device__ __forceinline__ void stsm4(uint32_t a, uint32_t r0, uint32_t r1, uint32_t r2, uint32_t r3) {
    asm volatile("stmatrix.sync.aligned.m8n8.x4.shared.b16 [%0], {%1,%2,%3,%4};" ::"r"(a), "r"(r0), "r"(r1), "r"(r2), "r"(r3) : "memory");
}
__device__ __forceinline__ void sts128(uint32_t a, uint32_t r0, uint32_t r1, uint32_t r2, uint32_t r3) {
    asm volatile("st.shared.v4.b32 [%0], {%1,%2,%3,%4};" ::"r"(a), "r"(r0), "r"(r1), "r"(r2), "r"(r3) : "memory");
}
__device__ __forceinline__ void fence_async_smem() { asm volatile("fence.proxy.async.shared::cta;" ::: "memory"); }
__device__ __forceinline__ void fence_async_gmem() { asm volatile("fence.proxy.async.global;" ::: "memory"); }
__device__ __forceinline__ bool elect() {
    uint32_t p;
    asm volatile("{.reg .pred p; elect.sync _|p, 0xffffffff; selp.u32 %0, 1, 0, p;}" : "=r"(p));
    return p;
}
__device__ __forceinline__ uint32_t mapa(uint32_t a, uint32_t rank) { uint32_t r; asm("mapa.shared::cluster.u32 %0, %1, %2;" : "=r"(r) : "r"(a), "r"(rank)); return r; }
__device__ __forceinline__ void bulk_s2peer(uint32_t dst, uint32_t src, uint32_t bytes, uint32_t bar) {
    asm volatile("cp.async.bulk.shared::cluster.shared::cta.mbarrier::complete_tx::bytes [%0], [%1], %2, [%3];" ::"r"(dst), "r"(src), "r"(bytes), "r"(bar) : "memory");
}
__device__ __forceinline__ void bulk_s2g(void* dst, uint32_t src, uint32_t bytes) {
    asm volatile("cp.async.bulk.global.shared::cta.bulk_group [%0], [%1], %2;" ::"l"(dst), "r"(src), "r"(bytes) : "memory");
}
__device__ __forceinline__ void lds128(uint32_t a, uint32_t& r0, uint32_t& r1, uint32_t& r2, uint32_t& r3) {
    asm volatile("ld.shared.v4.b32 {%0,%1,%2,%3}, [%4];" : "=r"(r0), "=r"(r1), "=r"(r2), "=r"(r3) : "r"(a) : "memory");
}
__device__ __forceinline__ uint32_t lds32(uint32_t a) { uint32_t r; asm volatile("ld.shared.u32 %0, [%1];" : "=r"(r) : "r"(a) : "memory"); return r; }
__device__ __forceinline__ uint32_t hmul2(uint32_t a, uint32_t b) { uint32_t r; asm("mul.rn.f16x2 %0, %1, %2;" : "=r"(r) : "r"(a), "r"(b)); return r; }
__device__ __forceinline__ void stg128(void* p, uint32_t x, uint32_t y, uint32_t z, uint32_t w) {
    asm volatile("st.global.v4.b32 [%0], {%1,%2,%3,%4};" ::"l"(p), "r"(x), "r"(y), "r"(z), "r"(w) : "memory");
}
__device__ __forceinline__ void stg64(void* p, uint32_t x, uint32_t y) { asm volatile("st.global.v2.b32 [%0], {%1,%2};" ::"l"(p), "r"(x), "r"(y) : "memory"); }
__device__ __forceinline__ void bar_sync(int id, int n) { asm volatile("bar.sync %0, %1;" ::"r"(id), "r"(n) : "memory"); }
__device__ __forceinline__ void bar_arrive(int id, int n) { asm volatile("bar.arrive %0, %1;" ::"r"(id), "r"(n) : "memory"); }
__device__ __forceinline__ void warp_release(unsigned* f) {
    __syncwarp();
    if (lane_id() == 0) asm volatile("red.release.gpu.global.add.u32 [%0], 1;" ::"l"(f) : "memory");
    __syncwarp();
}
template <int SLEEP = 0>
__device__ __forceinline__ void flag_wait(const unsigned* f, unsigned target) {
#pragma unroll 1
    for (int n = 0;; n++) {
        unsigned v;
        asm volatile("ld.acquire.gpu.global.u32 %0, [%1];" : "=r"(v) : "l"(f) : "memory");
        if (__all_sync(~0u, (int)(v - target) >= 0) || n > (1 << 22)) break;
        if (SLEEP) __nanosleep(SLEEP);
    }
}
__device__ __forceinline__ uint32_t pack_h(float lo, float hi) { uint32_t r; asm("cvt.rn.f16x2.f32 %0, %1, %2;" : "=r"(r) : "f"(hi), "f"(lo)); return r; }
__device__ __forceinline__ uint32_t pack_b(float lo, float hi) { uint32_t r; asm("cvt.rn.bf16x2.f32 %0, %1, %2;" : "=r"(r) : "f"(hi), "f"(lo)); return r; }
__device__ __forceinline__ float h_lo(uint32_t v) { return __half2float(__ushort_as_half((unsigned short)(v & 0xFFFF))); }
__device__ __forceinline__ float h_hi(uint32_t v) { return __half2float(__ushort_as_half((unsigned short)(v >> 16))); }
__device__ __forceinline__ uint32_t hfma2(uint32_t a, uint32_t b, uint32_t c) { uint32_t r; asm("fma.rn.f16x2 %0, %1, %2, %3;" : "=r"(r) : "r"(a), "r"(b), "r"(c)); return r; }
__device__ __forceinline__ uint32_t hfma2_relu(uint32_t a, uint32_t b, uint32_t c) { uint32_t r; asm("fma.rn.relu.f16x2 %0, %1, %2, %3;" : "=r"(r) : "r"(a), "r"(b), "r"(c)); return r; }
__device__ __forceinline__ uint32_t ex2_h2(uint32_t x) { uint32_t y; asm("ex2.approx.f16x2 %0, %1;" : "=r"(y) : "r"(x)); return y; }
__device__ __forceinline__ float sqrt_approx(float x) { float y; asm("sqrt.approx.f32 %0, %1;" : "=f"(y) : "f"(x)); return y; }
__device__ __forceinline__ float ex2_f(float x) { float y; asm("ex2.approx.ftz.f32 %0, %1;" : "=f"(y) : "f"(x)); return y; }

constexpr float QSCALE = 0.27264373542131126f;
constexpr uint32_t KC = 0x78000035u;
constexpr float PSCALE = 0.0189666748046875f;
constexpr float XMAX = 15.4f;
constexpr float BMAX = 23.f;
__host__ __device__ constexpr bool is_poly(int blk) { return (PMASK >> blk) & 1; }

__device__ __forceinline__ uint32_t exp2_fma(uint32_t a, uint32_t kc) {
    uint32_t t, r;
    asm("{.reg .b16 l, h; .reg .b32 m; mov.b32 {l, h}, %2; mov.b32 m, {l, l}; fma.rn.relu.f16x2 %0, %1, m, %3;}" : "=r"(t) : "r"(a), "r"(kc), "r"(0x000D000Du));
    asm("{.reg .b16 l, h; .reg .b32 m; mov.b32 {l, h}, %2; mov.b32 m, {h, h}; fma.rn.f16x2 %0, %1, m, %3;}" : "=r"(r) : "r"(t), "r"(kc), "r"(0xA739A739u));
    const uint32_t u = hfma2(r, 0xC8DBC8DBu, a);
    const uint32_t w = hfma2(u, u, 0x18851885u);
    const uint32_t p = hfma2_relu(w, u, 0x02AF02AFu);
    return p + __funnelshift_l(t, t, 10);
}
__device__ __forceinline__ uint32_t phi2(float t0, float t1) {
    const uint32_t e = pack_b(__saturatef(ex2_f(t0 * 1.4426950408889634f) + 1e-6f), __saturatef(ex2_f(t1 * 1.4426950408889634f) + 1e-6f));
    uint32_t r;
    asm("{.reg .b32 t; cvt.rn.relu.bf16x2.f32 t, %1, %2; add.rn.bf16x2 %0, t, %3;}" : "=r"(r) : "f"(t1), "f"(t0), "r"(e));
    return r;
}

__device__ __forceinline__ uint4* o_slot(uint4* img, int par, int hp, int wq) {
    LANES;
    uint4* p = img + (7 * hp + (q == 3 ? 3 : q + 4 * par)) * 64 + wq * 16 + g;
    return q == 3 ? (uint4*)((uint2*)p + par) : p;
}
__device__ __forceinline__ void put_o(const float* o, float l0, float l1, int par, int q, uint4* p0, uint32_t (&a)[4], uint32_t (&b)[4]) {
    float i0, i1;
    asm("rcp.approx.ftz.f32 %0, %1;" : "=f"(i0) : "f"(l0));
    asm("rcp.approx.ftz.f32 %0, %1;" : "=f"(i1) : "f"(l1));
#pragma unroll
    for (int j = 0; j < 4; j++) {
        a[j] = pack_b(o[4 * j] * i0, o[4 * j + 1] * i0);
        b[j] = pack_b(o[4 * j + 2] * i1, o[4 * j + 3] * i1);
    }
    if (q == 3 && par) { a[0] = a[2]; a[1] = a[3]; b[0] = b[2]; b[1] = b[3]; }
    if (q < 3) {
        stg128(p0, a[0], a[1], a[2], a[3]);
        stg128(p0 + 8, b[0], b[1], b[2], b[3]);
    }
    else {
        stg64(p0, a[0], a[1]);
        stg64(p0 + 8, b[0], b[1]);
    }
}
__device__ __forceinline__ bool store_o(const float* o, int par, uint4* p0) {
    LANES;
    const float l0 = __shfl_sync(~0u, par ? o[0] : o[8], lane | 3), l1 = __shfl_sync(~0u, par ? o[2] : o[10], lane | 3);
    uint32_t a[4], b[4];
    put_o(o, l0, l1, par, q, p0, a, b);
    const uint32_t m23 = q == 3 ? 0u : 0x7FFF7FFFu;
    const uint32_t ma = __vmaxu2(__vmaxu2(a[0] & 0x7FFF7FFFu, a[1] & 0x7FFF7FFFu), __vmaxu2(a[2] & m23, a[3] & m23));
    const uint32_t mb = __vmaxu2(__vmaxu2(b[0] & 0x7FFF7FFFu, b[1] & 0x7FFF7FFFu), __vmaxu2(b[2] & m23, b[3] & m23));
    uint32_t m = __vmaxu2(__byte_perm(ma, mb, 0x5410), __byte_perm(ma, mb, 0x7632));
    m = __vmaxu2(m, __shfl_xor_sync(~0u, m, 1));
    m = __vmaxu2(m, __shfl_xor_sync(~0u, m, 2));
    return __any_sync(~0u, __vminu2(m, 0x7F7F7F7Fu) != m || __vmaxu2(m, 0x38003800u) != m);
}

__device__ __forceinline__ void mma16816(float* d, uint32_t a0, uint32_t a1, uint32_t a2, uint32_t a3, uint32_t b0, uint32_t b1) {
    asm volatile("mma.sync.aligned.m16n8k16.row.col.f32.bf16.bf16.f32 {%0,%1,%2,%3}, {%4,%5,%6,%7}, {%8,%9}, {%0,%1,%2,%3};"
                 : "+f"(d[0]), "+f"(d[1]), "+f"(d[2]), "+f"(d[3]) : "r"(a0), "r"(a1), "r"(a2), "r"(a3), "r"(b0), "r"(b1));
}
__device__ __forceinline__ void mma16816h(float* d, uint32_t a0, uint32_t a1, uint32_t a2, uint32_t a3, uint32_t b0, uint32_t b1) {
    asm volatile("mma.sync.aligned.m16n8k16.row.col.f32.f16.f16.f32 {%0,%1,%2,%3}, {%4,%5,%6,%7}, {%8,%9}, {%0,%1,%2,%3};"
                 : "+f"(d[0]), "+f"(d[1]), "+f"(d[2]), "+f"(d[3]) : "r"(a0), "r"(a1), "r"(a2), "r"(a3), "r"(b0), "r"(b1));
}
__device__ __forceinline__ uint32_t movm(uint32_t a) { uint32_t d; asm volatile("movmatrix.sync.aligned.m8n8.trans.b16 %0, %1;" : "=r"(d) : "r"(a)); return d; }

__device__ __forceinline__ void safe_rows(float (&of)[16], const uint32_t (&qf)[8], const bool recompute, const uint32_t* x, const uint32_t* w, const uint32_t* kvg,
                                          const int h, const int row0) {
    LANES;
    const int par = h & 1;
    uint32_t qb[8], kv[16];
#pragma unroll
    for (int j = 0; j < 8; j++) qb[j] = (j >= 6 && (q >> 1) != par) ? 0u : qf[j];
    float m0 = -3e38f, m1 = -3e38f;
#pragma unroll
    for (int i = 0; i < 16; i++) of[i] = 0.f;
#pragma unroll 1
    for (int kb = recompute ? -1 : 0; kb < 128; kb++) {
        float k0 = QSCALE, k1 = QSCALE;
        if (recompute) {
#pragma unroll 1
            for (int part = kb < 0 ? 0 : 1; part < (kb < 0 ? 1 : 3); part++) {
                float acc[16];
#pragma unroll
                for (int i = 0; i < 16; i++) acc[i] = 0.f;
                const uint32_t* xr = x + ((kb < 0 ? row0 : kb * 16) + g) * 224 + q;
                const uint32_t* wr = w + g * 672 + part * 224 + (h >> 1) * 28;
#pragma unroll 1
                for (int ks = 0; ks < 28; ks++) {
                    const uint32_t a0 = xr[ks * 8], a1 = xr[ks * 8 + 1792], a2 = xr[ks * 8 + 4], a3 = xr[ks * 8 + 1796];
#pragma unroll
                    for (int j = 0; j < 4; j++) {
                        const int pp = part == 2 ? 4 * q + j : 4 * j + q;
                        const uint32_t* wc = wr + ks * 10752 + (par && pp < 12 ? 16 + pp : pp);
                        mma16816(acc + 4 * j, a0, a1, a2, a3, movm(wc[0]), movm(wc[5376]));
                    }
                }
#pragma unroll
                for (int j = 0; j < 4; j++) {
                    const int pp = part == 2 ? 4 * q + j : 4 * j + q;
                    const bool real = pp < 12 || (pp >= 14) == (par != 0);
                    const uint32_t pad = (part == 2 && !(pp & 1)) ? 0x3F80u : 0u;
                    const uint32_t r0 = real ? pack_b(acc[4 * j], acc[4 * j + 1]) : pad, r1 = real ? pack_b(acc[4 * j + 2], acc[4 * j + 3]) : pad;
                    if (part == 0) { qb[2 * j] = r0; qb[2 * j + 1] = r1; }
                    else if (part == 1) { kv[2 * j] = r0; kv[2 * j + 1] = r1; }
                    else { kv[8 + 2 * j] = r0; kv[9 + 2 * j] = r1; }
                }
            }
            if (kb < 0) continue;
        } else {
            const uint32_t* r = kvg + (h * 2048 + kb * 16 + g) * 32 + q;
            k0 = (PMASK >> ((2 * kb) & 15)) & 1 ? 1.f / PSCALE : 1.f; k1 = (PMASK >> ((2 * kb + 1) & 15)) & 1 ? 1.f / PSCALE : 1.f;
#pragma unroll
            for (int j = 0; j < 8; j++) {
                kv[2 * j] = r[(j ^ g) * 4];
                kv[2 * j + 1] = r[256 + (j ^ g) * 4];
            }
        }
        float s[8];
#pragma unroll
        for (int i = 0; i < 8; i++) s[i] = 0.f;
#pragma unroll
        for (int t = 0; t < 2; t++) {
            if (recompute) {
                mma16816(s + 4 * t, qb[0], qb[1], qb[2], qb[3], kv[t], kv[2 + t]);
                mma16816(s + 4 * t, qb[4], qb[5], qb[6], qb[7], kv[4 + t], kv[6 + t]);
            } else {
                mma16816h(s + 4 * t, qb[0], qb[1], qb[2], qb[3], kv[t], kv[2 + t]);
                mma16816h(s + 4 * t, qb[4], qb[5], qb[6], qb[7], kv[4 + t], kv[6 + t]);
            }
        }
#pragma unroll
        for (int i = 0; i < 8; i++) s[i] = __fmul_rn(s[i], i < 4 ? k0 : k1);
        float n0 = fmaxf(fmaxf(s[0], s[1]), fmaxf(s[4], s[5])), n1 = fmaxf(fmaxf(s[2], s[3]), fmaxf(s[6], s[7]));
        n0 = fmaxf(n0, __shfl_xor_sync(~0u, n0, 1)); n1 = fmaxf(n1, __shfl_xor_sync(~0u, n1, 1));
        n0 = fmaxf(fmaxf(n0, __shfl_xor_sync(~0u, n0, 2)), m0); n1 = fmaxf(fmaxf(n1, __shfl_xor_sync(~0u, n1, 2)), m1);
        const float c0 = ex2_f(m0 - n0), c1 = ex2_f(m1 - n1);
        m0 = n0; m1 = n1;
        uint32_t pa[4];
#pragma unroll
        for (int i = 0; i < 4; i++) {
            const float m = (i & 1) ? m1 : m0;
            const float e0 = ex2_f(s[2 * i] - m), e1 = ex2_f(s[2 * i + 1] - m);
            pa[i] = recompute ? pack_b(e0, e1) : pack_h(e0 * 1024.f, e1 * 1024.f);
        }
#pragma unroll
        for (int j = 0; j < 4; j++) {
            of[4 * j] *= c0; of[4 * j + 1] *= c0; of[4 * j + 2] *= c1; of[4 * j + 3] *= c1;
            const uint32_t b0 = movm(kv[8 + 2 * j]), b1 = movm(kv[9 + 2 * j]);
            if (recompute) mma16816(of + 4 * j, pa[0], pa[1], pa[2], pa[3], b0, b1);
            else mma16816h(of + 4 * j, pa[0], pa[1], pa[2], pa[3], b0, b1);
        }
    }
}

__device__ __forceinline__ void out_gemm(float (&acc)[56], uint32_t sb, int w) {
    zero(acc);
#pragma unroll 1
    for (int kc = 0; kc < 7; kc++) {
        uint64_t da = desc_plain(sb + o_off(w, kc), 1024, 128), db = desc128(sb + wo_off(kc), 8192);
        mbar_wait(sb + SM_BAR + 8 * (B_WO + kc));
        mbar_wait(sb + SM_BAR + 8 * (B_O + 7 * w + kc));
        WG_FENCE();
#pragma unroll
        for (int ks = 0; ks < 4; ks++) mma_bf16_ss_n112(acc, da + ks * 128, db + ks * 128, 1);
        WG_COMMIT();
    }
    WG_WAIT(0);
    pin(acc);
}
__device__ __forceinline__ void out_store(float (&acc)[56], uint32_t stage, uint8_t* out, int col, int row) {
    const int lane = lane_id();
    const uint32_t a = stage + (lane & 15) * 240 + (lane >> 4) * 16;
#pragma unroll
    for (int j = 0; j < 7; j++)
        stsm4(a + j * 32, pack_b(acc[8 * j], acc[8 * j + 1]), pack_b(acc[8 * j + 2], acc[8 * j + 3]),
              pack_b(acc[8 * j + 4], acc[8 * j + 5]), pack_b(acc[8 * j + 6], acc[8 * j + 7]));
    __syncwarp();
    uint4 v[8];
    const int r = lane >> 4, ch = lane & 15;
    uint8_t* dst = out + (row + r) * 1792 + col * 2 + ch * 16;
    if (ch < 14) {
#pragma unroll
        for (int j = 0; j < 8; j++) lds128(stage + (2 * j + r) * 240 + ch * 16, v[j].x, v[j].y, v[j].z, v[j].w);
#pragma unroll
        for (int j = 0; j < 8; j++) stg128(dst + j * 3584, v[j].x, v[j].y, v[j].z, v[j].w);
    }
}

__global__ void __cluster_dims__(2, 1, 1) __launch_bounds__(NTHREADS, 1) fused_kernel(const __grid_constant__ Params P) {
    extern __shared__ __align__(1024) uint8_t smem[];
    const uint32_t sb = (uint32_t)__cvta_generic_to_shared(smem);
    const int warp = __shfl_sync(~0u, threadIdx.x >> 5, 0), wg = warp >> 2, wq = warp & 3;
    const int bx = blockIdx.x;
    const int ck = bx >> 1;
    const int k7 = (ck - 36) * 37 >> 8;
    const int slot = ck < 4 ? 4 + ck : ck < 36 ? (ck - 4) >> 3 : 4 + k7;
    const int grp = ck < 4 ? 0 : ck < 36 ? (ck - 4) & 7 : ck - 35 - 7 * k7;
    const int c = ck >= 64 ? 2 * ck + (bx & 1) : (bx & 1) | ((HPORD >> (4 * slot)) & 7) << 1 | grp << 4;
    const int rank = c & 1, hp = (c >> 1) & 7, rb128 = (c >> 4) * 2 + rank;
    const int h = 2 * hp + rank;
    const int tcb = (c >> 1) & 3;
    auto BAR = [&](int i) { return sb + SM_BAR + 8 * i; };
    __builtin_assume(__isGlobal(P.s));

    auto load_chunk = [&](const int n) {
        const int b = n < NB1 || n >= NB1 + 7, kc = n < NB1 ? n : n < NB1 + 7 ? n - NB1 : n - 7;
        if (XFIRST) tma2d(sb + x_off(n), &P.x[b], kc * 64, rb128 * 128, BAR(B_FULL + n));
        tma3d_mc(sb + w_off(n) + rank * 12288, &P.w[b], hp * 56, kc * 64 + rank * 32, 0, BAR(B_FW + n));
        if (!XFIRST) tma2d(sb + x_off(n), &P.x[b], kc * 64, rb128 * 128, BAR(B_FULL + n));
    };
    if (warp == 16) {
        if (elect()) {
            asm volatile("prefetch.tensormap [%0];" ::"l"(&P.w[1]) : "memory");
            asm volatile("prefetch.tensormap [%0];" ::"l"(&P.x[1]) : "memory");
#pragma unroll
            for (int n = 0; n < NPRO; n++) { mbar_init(BAR(B_FW + n), 1); mbar_init(BAR(B_FULL + n), 2); }
#pragma unroll
            for (int n = 0; n < NPRO; n++) { mbar_expect(BAR(B_FW + n), 21504); mbar_expect(BAR(B_FULL + n), 16384); }
            asm volatile("fence.mbarrier_init.release.cluster;" ::: "memory");
        }
        __syncwarp();
    }
    asm volatile("barrier.cluster.arrive.relaxed.aligned;" ::: "memory");
    if (warp == 16) {
        asm volatile("barrier.cluster.wait.aligned;\nbarrier.cluster.arrive.relaxed.aligned;" ::: "memory");
        if (c < NWORK && elect()) {
#pragma unroll
            for (int n = 0; n < NPRO; n++) load_chunk(n);
        }
        __syncwarp();
    } else {
        if (warp < 16) {
            if (elect()) {
                const uint32_t b0 = BAR(warp);
                if (warp >= NPRO) { mbar_init(b0, warp < 14 ? 2 : 1); mbar_init(b0 + 640, 1); mbar_expect(b0 + 640, 21504); }
                mbar_init(b0 + 128, 1); mbar_init(b0 + 256, 1);
                mbar_init(b0 + 384, warp == B_QR - 48 ? 8 : warp == B_BD - 48 ? 2 : warp >= B_LI - 48 ? 1 : warp < 8 ? 16 : 4); mbar_init(b0 + 512, 4);
                if (warp >= NPRO && warp != B_G) mbar_expect(b0, warp == B_Q ? 8224 : 16384);
                mbar_expect(b0 + 128, warp < 2 ? 16384 : warp == 2 ? 49152 : warp < 8 ? 32768 : 14336);
                if (warp != B_ACK - 32) mbar_expect(b0 + 256, 8192);
                asm volatile("st.shared.u32 [%0], %1;" ::"r"(sb + SM_KG + 8), "r"(KC) : "memory");
                asm volatile("fence.mbarrier_init.release.cluster;" ::: "memory");
            }
        }
        __syncwarp();
        asm volatile("barrier.cluster.wait.aligned;\nbarrier.cluster.arrive.relaxed.aligned;" ::: "memory");
    }
    asm volatile("barrier.cluster.wait.aligned;" ::: "memory");

    if (wg == 4) {
        asm volatile("setmaxnreg.dec.sync.aligned.u32 32;");
        if (c < NWORK) {
            uint8_t* kvh = (uint8_t*)(g_KV + h * 2048 * 8);
            uint8_t* kvo = (uint8_t*)(g_KV + (h ^ 1) * 2048 * 8);
            auto get_epoch = [&]() { return *(volatile unsigned*)&g_flag[F_EPOCH + c * 8] + 1; };
            auto load_o = [&](const int w, const unsigned epoch) {
                const int trow = (c >> 4) * 4 + ((c >> 3) & 1) + 2 * w;
                const uint4* src = g_O + (rank * 32 + trow) * 3584;
                const unsigned* f = &g_flag[F_O + (rank ? (trow & ~1) * 32 + 8 : trow * 32) + (lane_id() & 7)];
                const unsigned target = epoch * (2 - rank);
                mbar_wait(BAR(B_D + 6 + w));
                int kc = 0;
#pragma unroll 1
                for (int n = 0; kc < 7; n++) {
                    unsigned v;
                    asm volatile("ld.acquire.gpu.global.u32 %0, [%1];" : "=r"(v) : "l"(f) : "memory");
                    const int ready = __ffs(__ballot_sync(~0u, (int)(v - target) < 0 && n < (1 << 22)) | 256) - 2;
                    if (kc < ready) {
                        if (w) mbar_wait(BAR(B_D + 8));
                        if (elect()) {
                            fence_async_gmem();
#pragma unroll
                            for (int k = 0; k < 7; k++)
                                if (k >= kc && k < ready) bulk_g2s(sb + o_off(w, k), src + k * 512, 8192, BAR(B_O + 7 * w + k));
                        }
                        __syncwarp();
                        kc = ready;
                    }
                }
            };
            auto fill = [&]() {
                const int lane = lane_id();
#pragma unroll 1
                for (int n = wq & 1; n < 14; n += 2) {
                    const uint32_t a = sb + w_off(n) + lane * 128 + ((7 ^ (lane & 7)) << 4);
                    uint32_t v[8];
                    mbar_wait(BAR(B_FW + n));
                    lds128((a ^ 16) + 8192, v[0], v[1], v[2], v[3]);
                    lds128((a ^ 16) + 8192 + 12288, v[4], v[5], v[6], v[7]);
                    sts128(a, v[0], v[1], v[2], v[3]);
                    sts128(a + 12288, v[4], v[5], v[6], v[7]);
                    fence_async_smem();
                    __syncwarp();
                    if (elect()) mbar_arrive(BAR(B_FULL + n));
                    __syncwarp();
                }
            };
            if (wq >= 2) fill();
            if (wq == 0) {
#pragma unroll 1
                for (int n = NPRO; n < 14; n++) {
                    if (n >= LOOK) mbar_wait(BAR(B_EM + n - (n < LOOKN ? LOOK : NSLOT)));
                    if (elect()) load_chunk(n);
                    __syncwarp();
                }
                const unsigned epoch = get_epoch();
                auto load_pair = [&](const int i) { bulk_g2s(sb + pair_off(i), kvh + ((i + (rb128 >> 1)) & 7) * (2 * UNIT), 2 * UNIT, BAR(kp_bar(i))); };
                auto load_wo = [&](const int k) {
                    tma2d(sb + wo_off(k), &P.wo64[rank], tcb * 112, k * 64, BAR(B_WO + k));
                    tma2d(sb + wo_off(k) + 8192, &P.wo48[rank], tcb * 112 + 64, k * 64, BAR(B_WO + k));
                };
                mbar_wait(BAR(B_G));
                mbar_wait(BAR(B_BD));
                if (elect()) {
                    fence_async_gmem();
                    const uint8_t* src = kvh + ((1 + (rb128 >> 1)) & 7) * (2 * UNIT);
                    bulk_g2s(sb + pair_off(1), src, UNIT, BAR(kp_bar(1)));
                    bulk_g2s(sb + pair_off(1) + UNIT, src + UNIT, UNIT, BAR(kp_bar(2)));
                    load_pair(2);
                }
                __syncwarp();
                mbar_wait(BAR(kp_bar(2)));
                if (elect()) load_pair(3);
                __syncwarp();
#pragma unroll 1
                for (int d = 0; d < 5; d++) {
                    mbar_wait(BAR(B_D + 1 + d));
                    if (d == 0) mbar_wait(BAR(B_ACK));
                    if (elect()) {
                        if (d == 0) load_pair(4);
                        if (d < 3) load_pair(d + 5);
                        if (d > 0) load_wo(d < 3 ? d - 1 : 2 * d - 4);
                        if (d == 3 || d == 4) load_wo(2 * d - 3);
                    }
                    __syncwarp();
                }
                load_o(0, epoch);
            } else if (wq == 1) {
                if (elect()) {
                    asm volatile("prefetch.tensormap [%0];" ::"l"(&P.w[0]) : "memory");
                    asm volatile("prefetch.tensormap [%0];" ::"l"(&P.x[0]) : "memory");
                }
                __syncwarp();
                const unsigned epoch = get_epoch();
                const int lane = lane_id();
                bar_sync(7, 544);
                if (elect()) {
                    const uint32_t rsb = mapa(sb, rank ^ 1);
                    bulk_s2peer(rsb + 13 * UNIT + 8192, sb + 13 * UNIT, 8192, rsb + SM_BAR + 8 * B_Q);
                    bulk_s2peer(rsb + SM_KN + 64, sb + SM_KN, 32, rsb + SM_BAR + 8 * B_Q);
                    bulk_s2g(kvh + rb128 * UNIT, sb + 10 * UNIT, UNIT);
                    bulk_s2g(kvo + rb128 * UNIT, sb + 12 * UNIT, UNIT);
                    asm volatile("cp.async.bulk.commit_group;" ::: "memory");
                }
                __syncwarp();
                const uint32_t kn = min(lds32(sb + SM_KN + 4 * (lane & 15)), 0x7F800000u);
                const uint32_t kout = __reduce_max_sync(~0u, (lane & 8) ? 0u : kn), kown = __reduce_max_sync(~0u, (lane & 8) ? kn : 0u);
                if (elect()) {
                    asm volatile("cp.async.bulk.wait_group 0;" ::: "memory");
                    asm volatile("fence.release.gpu;" ::: "memory");
                    asm volatile("st.relaxed.gpu.global.u32 [%0], %1;" ::"l"(&g_flag[F_A + h * 32 + rb128]), "r"(((kown + 255) & ~255u) | (epoch & 255)) : "memory");
                    asm volatile("st.relaxed.gpu.global.u32 [%0], %1;" ::"l"(&g_flag[F_A + (h ^ 1) * 32 + rb128]), "r"(((kout + 255) & ~255u) | (epoch & 255)) : "memory");
                    mbar_arrive_rank(BAR(B_PAIR), rank ^ 1);
                }
                __syncwarp();
                {
                    mbar_wait(BAR(B_PAIR));
                    if (elect()) {
                        asm volatile("fence.acquire.gpu;" ::: "memory");
                        fence_async_gmem();
                        bulk_g2s(sb + 11 * UNIT, kvh + (rb128 ^ 1) * UNIT, UNIT, BAR(kp_bar(0)));
                    }
                    __syncwarp();
                }
                mbar_wait(BAR(B_Q));
                if (elect()) mbar_arrive_rank(BAR(B_ACK), rank ^ 1);
                __syncwarp();
                load_o(1, epoch);
                if (elect()) {
                    mbar_arrive(BAR(B_LI));
                    g_flag[F_EPOCH + c * 8] = epoch;
                }
            } else if (wq == 2) {
                if (elect()) {
                    asm volatile("prefetch.tensormap [%0];" ::"l"(&P.wo64[rank]) : "memory");
                    asm volatile("prefetch.tensormap [%0];" ::"l"(&P.wo48[rank]) : "memory");
                }
                __syncwarp();
                const unsigned epoch = get_epoch();
                bar_sync(6, 160);
                warp_release(&g_flag[F_B + hp * 32]);
                flag_wait<200>(&g_flag[F_Z + hp * 32], epoch * 8);
                mbar_wait(BAR(B_G));
                if (elect()) {
                    fence_async_gmem();
                    bulk_g2s(sb + 12 * UNIT, g_KVZ + hp * 2048, 8192, BAR(B_Z));
                }
                __syncwarp();
                bar_sync(9, 288);
                warp_release(&g_flag[F_O + rb128 * 64 + 8 + hp]);
            } else {
                const unsigned epoch = get_epoch();
                const int lane = lane_id();
                mbar_wait(BAR(B_Q));
                uint32_t v;
#pragma unroll 1
                for (int n = 0;; n++) {
                    asm volatile("ld.acquire.gpu.global.u32 %0, [%1];" : "=r"(v) : "l"(&g_flag[F_A + h * 32 + (lane & 15)]) : "memory");
                    if (__all_sync(~0u, ((v ^ epoch) & 255) == 0) || n > (1 << 22)) break;
                }
                v = __reduce_max_sync(~0u, v);
                if (elect()) {
                    asm volatile("st.shared.u32 [%0], %1;" ::"r"(sb + SM_KG), "r"(v) : "memory");
                    mbar_arrive(BAR(B_G));
                }
                __syncwarp();
                mbar_wait(BAR(B_D + 7));
                if (elect()) {
                    tma2d(sb + wo_off(6), &P.wo64[rank], tcb * 112, 384, BAR(B_WO + 6));
                    tma2d(sb + wo_off(6) + 8192, &P.wo48[rank], tcb * 112 + 64, 384, BAR(B_WO + 6));
                }
                __syncwarp();
            }
        }
    } else {
        asm volatile("setmaxnreg.inc.sync.aligned.u32 112;");
        if (c >= NWORK) {
            LANES;
            const int pr = (c - NWORK) * 2 + (wg >> 1), hf = wg & 1, t = wq * 32 + lane;
            const unsigned epoch = *(volatile unsigned*)&g_flag[F_EPOCH + c * 8] + 1;
            flag_wait<100>(&g_flag[F_B + pr * 32], epoch * 16);
            float d[8];
#pragma unroll
            for (int i = 0; i < 8; i++) d[i] = 0.f;
#pragma unroll 8
            for (int r = 0; r < 16; r++) {
#pragma unroll
                for (int i = 0; i < 2; i++) {
                    float4 v = __ldcg(&g_KVP[((pr * 16 + r) * 4 + hf * 2 + i) * 128 + t]);
                    d[4 * i] += v.x; d[4 * i + 1] += v.y; d[4 * i + 2] += v.z; d[4 * i + 3] += v.w;
                }
            }
            const int row = wq * 16 + hf * 8 + g, side = row >= 28;
            uint32_t* z = g_KVZ + pr * 2048 + row * 4 + q;
#pragma unroll
            for (int j = 0; j < 4; j++) {
                const uint32_t v = row < 56 ? pack_b(d[2 * j], d[2 * j + 1]) : 0u;
                z[j * 256] = side ? 0u : v;
                z[(4 + j) * 256] = side ? v : 0u;
            }
            warp_release(&g_flag[F_Z + pr * 32]);
            bar_sync(1, 512);
            if (threadIdx.x == 0) g_flag[F_EPOCH + c * 8] = epoch;
        } else {
            const int br = wg >> 1;
            const int w16 = (warp & 7) * 16;
            const uint64_t d0 = desc128(sb);
            auto qkv_gemm = [&](float (&acc)[60], float (&acv)[24], const int n0, const int n1) {
                auto release = [&](const int n) {
                    if (wq == 0 && (n < 10 || n == ASTART)) {
                        if (elect()) {
                            mbar_arrive(BAR(B_EM + n));
                            mbar_arrive_rank(BAR(B_EM + n), rank ^ 1);
                        }
                        __syncwarp();
                    }
                };
#pragma unroll 1
                for (int n = n0; n < n1; n++) {
                    const uint64_t db = d0 + (w_off(n) >> 4), da = d0 + (x_off(n) >> 4) + (wg & 1) * 512;
                    mbar_wait(BAR(B_FULL + n));
                    WG_FENCE();
#pragma unroll
                    for (int ks = 0; ks < 4; ks++) {
                        const int o = (ks >> 1) * 768 + (ks & 1) * 128;
                        mma_bf16_ss_n120(acc, da + ks * 2, db + o + (255 << 16), 1);
                        mma_bf16_ss_n48(acv, da + ks * 2, db + o + 512, 1);
                        if (ks == 0) {
                            WG_COMMIT();
                            WG_WAIT(1);
                            if (n > n0) release(n - 1);
                            WG_FENCE();
                        }
                    }
                    WG_COMMIT();
                }
                WG_WAIT(0);
                release(n1 - 1);
                pin(acc); pin(acv);
            };
            auto norm_max = [&](const uint32_t (&f)[8]) {
                uint32_t n0 = hmul2(f[0], f[0]), n1 = hmul2(f[1], f[1]);
#pragma unroll
                for (int j = 1; j < 4; j++) { n0 = hfma2(f[2 * j], f[2 * j], n0); n1 = hfma2(f[2 * j + 1], f[2 * j + 1], n1); }
                uint32_t n = hfma2(__byte_perm(n0, n1, 0x5410), 0x3C003C00u, __byte_perm(n0, n1, 0x7632));
                n = hfma2(__shfl_xor_sync(~0u, n, 1), 0x3C003C00u, n);
                n = hfma2(__shfl_xor_sync(~0u, n, 2), 0x3C003C00u, n);
                const uint32_t m = __reduce_max_sync(~0u, max(n & 0xFFFFu, n >> 16));
                return __float_as_uint(fmaf(h_lo(m), 1.01f, 1e-5f));
            };
            uint32_t qmax, kloc, qf[8];
            if (br == 0) {
                float acc[60], acv[24];
                float (&aq)[28] = *(float (*)[28])acc;
                float (&ak)[28] = *(float (*)[28])(acc + 32);
                zero(acc); zero(acv);
                auto av = [&](const int i) { return i < 24 ? acv[i % 24] : acc[4 + i]; };
                if (AORD && NB1 >= AORD) mbar_wait(BAR(B_EM + NB1 - AORD));
                qkv_gemm(acc, acv, NB1, NB1 + 7);
                if (NSLOT == 5) mbar_wait(BAR(B_EM + 9));
                LANES;
                const float ks0 = (PMASK >> (2 * warp)) & 1 ? QSCALE * PSCALE : QSCALE, ks1 = (PMASK >> (2 * warp + 1)) & 1 ? QSCALE * PSCALE : QSCALE;
#pragma unroll
                for (int par = 0; par < 2; par++) {
                    const bool real3 = par ? q >= 2 : q < 2;
                    uint32_t a[4], b[4];
#pragma unroll
                    for (int j = 0; j < 4; j++) {
                        const int o = 4 * (j == 3 ? 3 : j + 4 * par);
                        a[j] = pack_h(av(o), av(o + 1));
                        b[j] = pack_h(av(o + 2), av(o + 3));
                    }
                    if (!real3) a[3] = b[3] = (q & 1) ? 0u : 0x3C00u;
                    const uint32_t va = sb + (par == rank ? 10 : 12) * UNIT + (w16 + g) * 128 + (((4 + q) ^ g) << 4);
                    sts128(va, a[0], a[1], a[2], a[3]);
                    sts128(va + 1024, b[0], b[1], b[2], b[3]);
                }
                pin(ak);
#pragma unroll
                for (int par = 0; par < 2; par++) {
                    const bool real3 = par ? q >= 2 : q < 2;
                    uint32_t a[4], b[4];
                    float n0 = 0.f, n1 = 0.f;
#pragma unroll
                    for (int j = 0; j < 4; j++) {
                        const int o = 4 * (j == 3 ? 3 : j + 4 * par);
                        float x0 = ak[o], x1 = ak[o + 1], y0 = ak[o + 2], y1 = ak[o + 3];
                        if (j == 3) { x0 = real3 ? x0 : 0.f; x1 = real3 ? x1 : 0.f; y0 = real3 ? y0 : 0.f; y1 = real3 ? y1 : 0.f; }
                        n0 = fmaf(x0, x0, fmaf(x1, x1, n0));
                        n1 = fmaf(y0, y0, fmaf(y1, y1, n1));
                        if (j == 3 && !real3 && !(q & 1)) { x0 = 1.f / QSCALE; y0 = 1.f / QSCALE; }
                        a[j] = pack_h(x0 * ks0, x1 * ks0);
                        b[j] = pack_h(y0 * ks1, y1 * ks1);
                    }
                    const uint32_t ka = sb + (par == rank ? 10 : 12) * UNIT + (w16 + (lane & 7)) * 128 + (((lane >> 3) ^ (lane & 7)) << 4);
                    stsm4(ka, a[0], a[1], a[2], a[3]);
                    stsm4(ka + 1024, b[0], b[1], b[2], b[3]);
                    n0 += __shfl_xor_sync(~0u, n0, 1); n1 += __shfl_xor_sync(~0u, n1, 1);
                    n0 += __shfl_xor_sync(~0u, n0, 2); n1 += __shfl_xor_sync(~0u, n1, 2);
                    const uint32_t m = __reduce_max_sync(~0u, max(__float_as_uint(n0), __float_as_uint(n1)));
                    asm volatile("st.shared.f32 [%0], %1;" ::"r"(sb + SM_KN + (par == rank ? 32 : 0) + 4 * warp), "f"(__uint_as_float(m) * (QSCALE * QSCALE)) : "memory");
                }
                {
                    uint32_t t[14], u[8];
#pragma unroll
                    for (int j = 0; j < 14; j++) t[j] = pack_h(aq[2 * j], aq[2 * j + 1]);
#pragma unroll
                    for (int j = 0; j < 6; j++) { qf[j] = rank ? t[8 + j] : t[j]; u[j] = rank ? t[j] : t[8 + j]; }
                    const bool own3 = (q >> 1) == rank;
                    qf[6] = own3 ? t[6] : 0u; qf[7] = own3 ? t[7] : 0u;
                    u[6] = own3 ? 0u : t[6]; u[7] = own3 ? 0u : t[7];
                    const uint32_t qa = sb + 13 * UNIT + warp * 1024 + lane * 16;
                    sts128(qa, u[0], u[1], u[2], u[3]);
                    sts128(qa + 512, u[4], u[5], u[6], u[7]);
                }
                fence_async_smem();
                bar_sync(7, 544);
                const uint32_t nown = norm_max(qf);
                mbar_wait(BAR(B_Q));
                uint32_t in[8];
                const uint32_t qa = sb + 13 * UNIT + 8192 + warp * 1024 + lane * 16;
                lds128(qa, in[0], in[1], in[2], in[3]);
                lds128(qa + 512, in[4], in[5], in[6], in[7]);
                kloc = __reduce_max_sync(~0u, lds32(sb + SM_KN + 32 + 4 * (lane & 15)));
                const uint32_t nin = norm_max(in);
                if (rank) {
                    sts128(qa, qf[0], qf[1], qf[2], qf[3]);
                    sts128(qa + 512, qf[4], qf[5], qf[6], qf[7]);
#pragma unroll
                    for (int k = 0; k < 8; k++) qf[k] = in[k];
                }
                qmax = __shfl_sync(~0u, rank ? nin : nown, 0);
                asm volatile("st.shared.v2.b32 [%0], {%1, %2};" ::"r"(sb + SM_QN + 8 * warp), "r"(rank ? nown : nin), "r"(kloc) : "memory");
                __syncwarp();
                if (elect()) mbar_arrive(BAR(B_QR));
                __syncwarp();
                if (ASTART) mbar_wait(BAR(B_EM + ASTART));
            } else {
                float acc[60], acv[24];
                float (&aq)[28] = *(float (*)[28])acc;
                float (&ak)[28] = *(float (*)[28])(acc + 32);
                zero(acc); zero(acv);
                auto av = [&](const int i) { return i < 24 ? acv[i % 24] : acc[4 + i]; };
#pragma unroll 1
                for (int r = 0; r < 2; r++) {
                    if (r) {
                        bar_sync(7, 544);
                    }
                    qkv_gemm(acc, acv, r ? NB1 + 7 : 0, r ? 14 : NB1);
                }
                if (wq == 0 && elect()) mbar_arrive(BAR(B_BD));
                __syncwarp();
                LANES;
                bar_sync(2 + wg, 128);
#pragma unroll
                for (int par = 0; par < 2; par++) {
                    const bool real3 = par ? q >= 2 : q < 2;
                    uint32_t x[4], y[4];
#pragma unroll
                    for (int j = 0; j < 4; j++) {
                        const int o = 4 * (j == 3 ? 3 : j + 4 * par);
                        x[j] = pack_b(av(o), av(o + 1));
                        y[j] = pack_b(av(o + 2), av(o + 3));
                    }
                    if (!real3) x[3] = y[3] = (q & 1) ? 0u : 0x3F80u;
                    const uint32_t ad = sb + UNIT + (w16 + g) * 128 + (((4 * par + q) ^ g) << 4);
                    sts128(ad, x[0], x[1], x[2], x[3]);
                    sts128(ad + 1024, y[0], y[1], y[2], y[3]);
                }
                const uint32_t xa = sb + (w16 + (lane & 15)) * 128 + (((lane >> 4) ^ (lane & 7)) << 4);
                auto put_phi = [&](float (&t)[28], uint32_t base) {
                    pin(t);
#pragma unroll
                    for (int j = 0; j < 4; j++) {
                        uint32_t a[4];
#pragma unroll
                        for (int i = 0; i < 4; i++) a[i] = 8 * j + 2 * i < 28 ? phi2(t[(8 * j + 2 * i) % 28], t[(8 * j + 2 * i + 1) % 28]) : 0u;
                        stsm4((xa + base) ^ (j << 5), a[0], a[1], a[2], a[3]);
                    }
                };
                put_phi(ak, 0);
                mbar_wait(BAR(B_QR));
                asm volatile("ld.shared.v2.b32 {%0, %1}, [%2];" : "=r"(qmax), "=r"(kloc) : "r"(sb + SM_QN + 8 * (warp - 8)) : "memory");
                qmax = __shfl_sync(~0u, qmax, 0); kloc = __shfl_sync(~0u, kloc, 0);
                const uint32_t qa = sb + 13 * UNIT + warp * 1024 + lane * 16;
                lds128(qa, qf[0], qf[1], qf[2], qf[3]);
                lds128(qa + 512, qf[4], qf[5], qf[6], qf[7]);
                put_phi(aq, 3 * UNIT);
                fence_async_smem();
                if (wg != KVWG) bar_arrive(1, KVWG < 2 ? 384 : 256);
            }

            const int par = rank;
            const int rb64 = (rb128 >> 1) * 4 + wg;
            uint32_t s[32], p[32], oh[8], o2[8];
            auto set_shift = [&](float km) {
                LANES;
                const int ql = par ? 0 : 2;
                const float old0 = -h_lo(__shfl_sync(~0u, qf[6], (lane & 28) | ql)), old1 = -h_lo(__shfl_sync(~0u, qf[7], (lane & 28) | ql));
                float n0 = 0.f, n1 = 0.f;
#pragma unroll
                for (int j = 0; j < 4; j++) {
                    const bool pad = j == 3 && q == ql;
                    float x0 = pad ? 0.f : h_lo(qf[2 * j]), x1 = h_hi(qf[2 * j]), y0 = pad ? 0.f : h_lo(qf[2 * j + 1]), y1 = h_hi(qf[2 * j + 1]);
                    n0 = fmaf(x0, x0, fmaf(x1, x1, n0));
                    n1 = fmaf(y0, y0, fmaf(y1, y1, n1));
                }
                n0 += __shfl_xor_sync(~0u, n0, 1); n1 += __shfl_xor_sync(~0u, n1, 1);
                n0 += __shfl_xor_sync(~0u, n0, 2); n1 += __shfl_xor_sync(~0u, n1, 2);
                const float s0 = fmaxf(ceilf(sqrt_approx(n0 * km) * 1.004f - XMAX), 0.f), s1 = fmaxf(ceilf(sqrt_approx(n1 * km) * 1.004f - XMAX), 0.f);
                if (q == ql) { qf[6] = pack_h(-s0, 0.f); qf[7] = pack_h(-s1, 0.f); }
                const float f0 = ex2_f(old0 - s0), f1 = ex2_f(old1 - s1);
                const uint32_t m0 = pack_h(f0, f0), m1 = pack_h(f1, f1);
#pragma unroll
                for (int k = 4 * EPV; k < 32; k++) p[k] = hmul2(p[k], (k & 1) ? m1 : m0);
#pragma unroll
                for (int k = 0; k < 8; k++) oh[k] = hmul2(oh[k], (k & 1) ? m1 : m0);
            };
            const uint32_t kc = lds32(sb + SM_KG + 8);
            auto expo = [&](const int k0, const int k1) {
#pragma unroll
                for (int k = 4 * k0; k < 4 * k1; k++) { p[k] = is_poly(k >> 1) ? exp2_fma(s[k], kc) : ex2_h2(s[k]); asm volatile("" : "+r"(p[k])::"memory"); }
            };
            auto mma_qk = [&](uint64_t dk) {
                mma_qk_h128(s, qf[0], qf[1], qf[2], qf[3], dk, 0);
                mma_qk_h128(s, qf[4], qf[5], qf[6], qf[7], dk + 2, 1);
            };
            auto mma_pv = [&](uint64_t dv, const int k0, const int k1, bool first) {
#pragma unroll
                for (int kk = k0; kk < k1; kk++) mma_pv_h32(oh, p[4 * kk], p[4 * kk + 1], p[4 * kk + 2], p[4 * kk + 3], dv + 4 + kk * 128, kk > 0 || !first);
            };
            zero(s); zero(p); zero(oh); zero(o2);
            auto full = [](uint32_t lo) { uint64_t d; asm("mov.b64 %0, {%1, %2};" : "=l"(d) : "r"(lo), "n"(0x40000040)); return d; };
            uint32_t lcur = (uint32_t)d0 + 10 * 1024, lprev = lcur - 1024;
            uint32_t units = PAIR_UNIT | 0x11u | (wg == KVWG ? 1u << (4 * KVIT) : 0u) | (wg == MIDWG0 ? 1u << (4 * MIDIT0) : 0u) | (wg == MIDWG1 ? 1u << (4 * MIDIT1) : 0u);
#pragma unroll 1
            for (uint32_t bp = BAR(0); units; bp += 8) {
                if (__builtin_expect((int)(units << 31) < 0, 0)) {
                    const int it = (bp - BAR(0)) >> 3;
                    WG_WAIT(0);
                    pin(oh);
                    if (it == KVIT && wg == KVWG) {
                        bar_sync(1, KVWG < 2 ? 384 : 256);
                        float d[32];
                        zero(d);
                        WG_FENCE();
#pragma unroll
                        for (int ks = 0; ks < 8; ks++) mma_bf16_ss_n64_tt(d, d0 + ks * 128, d0 + 1024 + ks * 128, 1);
                        WG_COMMIT();
                        WG_WAIT(0);
                        pin(d);
                        LANES;
                        float4* kp = g_KVP + (hp * 16 + rb128) * 512 + wq * 32 + lane;
                        const bool s0 = wq * 16 + g >= 28, s1 = wq * 16 + g + 8 >= 28;
#pragma unroll
                        for (int k = 0; k < 4; k++) {
                            uint32_t v[4];
#pragma unroll
                            for (int i = 0; i < 4; i++) {
                                const int o = 8 * (k & 1) + 2 * (k >> 1) + 4 * (i >> 1) + (i & 1);
                                asm("{.reg .pred p; setp.ne.b32 p, %3, 0; selp.b32 %0, %1, %2, p;}" : "=r"(v[i]) : "f"(d[16 + o]), "f"(d[o]), "r"((int)(k >> 1 ? s1 : s0)));
                            }
                            stg128(kp + k * 128, v[0], v[1], v[2], v[3]);
                        }
                        bar_arrive(6, 160);
                        zero(s);
                    }
                    if (it < 2) {
                        float km = __uint_as_float(kloc);
                        if (it) {
                            mbar_wait(BAR(B_G));
                            km = __uint_as_float(__shfl_sync(~0u, lds32(sb + SM_KG), 0));
                            mbar_wait(BAR(kp_bar(1)));
                        }
                        if (!(__uint_as_float(qmax) * km <= XMAX * XMAX * 0.99f)) set_shift(km);
                    } else {
                        const int hf = !(wg == MIDWG0 && it == MIDIT0);
                        float d[32];
                        mbar_wait(BAR(B_Z));
                        zero(d);
                        WG_FENCE();
#pragma unroll
                        for (int ks = 0; ks < 4; ks++) mma_bf16_ss_n64(d, d0 + 3 * 1024 + hf * 512 + ks * 2, desc_plain(sb + 12 * UNIT, 128, 1024) + ks * 16, 1);
                        WG_COMMIT();
                        WG_WAIT(0);
                        pin(d);
                        LANES;
                        uint4* dst = g_O + (32 + rb128 * 2 + hf) * 3584 + 7 * hp * 64 + wq * 16 + (q * 64 + g);
                        uint32_t a[16];
#pragma unroll
                        for (int k = 0; k < 4; k++) {
                            const float den = __shfl_sync(~0u, d[(k >> 1 ? 16 : 8) + 2 * (k & 1)], lane | 3) + 1e-6f;
                            float inv;
                            asm("rcp.approx.ftz.f32 %0, %1;" : "=f"(inv) : "f"(den));
#pragma unroll
                            for (int j = 0; j < 4; j++) {
                                const int o = 16 * (k >> 1) + 4 * j + 2 * (k & 1);
                                a[o >> 1] = pack_b(d[o] * inv, d[o + 1] * inv);
                            }
                        }
#pragma unroll
                        for (int r = 0; r < 2; r++) {
                            stg128(dst + 8 * r, a[r], a[2 + r], q == 3 ? a[12 + r] : a[4 + r], q == 3 ? a[14 + r] : a[6 + r]);
                            if (q < 3) stg128(dst + 256 + 8 * r, a[8 + r], a[10 + r], a[12 + r], a[14 + r]);
                        }
                        bar_arrive(9, 288);
                        zero(s);
                    }
                }
                pin(qf);
                WG_FENCE();
                mma_pv(full(lprev) + 1024, EPV, 8, false);
                mma_qk(full(lcur));
                WG_COMMIT();
                WG_WAIT(0);
                pin(s); pin(p); pin(oh);
                if (elect()) mbar_arrive(bp + 8 * B_D);
#pragma unroll
                for (int k = 0; k < 8; k++) o2[k] = hfma2(oh[k], 0x30003000u, o2[k]);
                pin(o2);
                lprev = lcur;
                units >>= 4;
                lcur = (uint32_t)d0 + (units & 14) * 1024;
                expo(0, EPV);
                WG_FENCE();
                mma_pv(full(lprev), 0, EPV, true);
                WG_COMMIT();
                expo(EPV, 8);
                mbar_wait(bp + 8 * (B_KP + 1));
                WG_FENCE();
                mma_pv(full(lprev), EPV, 8, true);
                mma_qk(full(lprev) + 1024);
                WG_COMMIT();
                WG_WAIT(0);
                pin(s); pin(p); pin(oh);
                expo(0, EPV);
                WG_FENCE();
                mma_pv(full(lprev) + 1024, 0, EPV, false);
                WG_COMMIT();
                expo(EPV, 8);
            }
            WG_FENCE();
            mma_pv(full(lprev) + 1024, EPV, 8, false);
            WG_COMMIT();
            const float qm = __uint_as_float(qmax), km = __uint_as_float(lds32(sb + SM_KG));
            const bool range_ok = qm < 65504.f && km <= 16777216.f;
            uint32_t ok = range_ok && qm * km <= BMAX * BMAX;
            uint4* optr = o_slot(g_O + rb64 * 3584, par, hp, wq);
            LANES;
            uint32_t m0 = q == 3 && par ? 0u : 0x7FFF7FFFu, m2 = q == 3 && !par ? 0u : 0x7FFF7FFFu;
            asm volatile("" : "+r"(ok), "+l"(optr), "+r"(m0), "+r"(m2)::"memory");
            WG_WAIT(0);
            pin(oh); pin(p);
            float of[16];
            uint32_t t[8];
#pragma unroll
            for (int i = 0; i < 8; i++) {
                t[i] = hfma2(oh[i], 0x30003000u, o2[i]);
                of[2 * i] = h_lo(t[i]); of[2 * i + 1] = h_hi(t[i]);
            }
            const uint32_t l = __shfl_sync(~0u, __byte_perm(par ? t[0] : t[4], par ? t[1] : t[5], 0x5410), lane | 3);
            const uint32_t ma = __vmaxu2(__vmaxu2(t[0] & m0, t[2] & 0x7FFF7FFFu), __vmaxu2(t[4] & m2, t[6] & 0x7FFF7FFFu));
            const uint32_t mb = __vmaxu2(__vmaxu2(t[1] & m0, t[3] & 0x7FFF7FFFu), __vmaxu2(t[5] & m2, t[7] & 0x7FFF7FFFu));
            uint32_t m = __vmaxu2(__byte_perm(ma, mb, 0x5410), __byte_perm(ma, mb, 0x7632));
            m = __vmaxu2(m, __shfl_xor_sync(~0u, m, 1));
            m = __vmaxu2(m, __shfl_xor_sync(~0u, m, 2));
            {
                uint32_t a[4], b[4];
                put_o(of, h_lo(l), h_hi(l), par, q, optr, a, b);
            }
            const uint32_t hi = __vmaxu2(m, l), big = m + 0x3C003C00u;
            const bool sums_ok = ok && __vminu2(hi, 0x7BFF7BFFu) == hi && __vmaxu2(l, 0x48004800u) == l;
            if (__builtin_expect(!__all_sync(~0u, sums_ok && __vmaxu2(big, l) == big), 0)) {
#pragma unroll 1
                for (int tier = !range_ok || __all_sync(~0u, sums_ok); tier < 2; tier++) {
                    safe_rows(of, qf, tier, (const uint32_t*)P.in[0], (const uint32_t*)P.in[1], (const uint32_t*)g_KV, h, rb64 * 64 + wq * 16);
                    if (!store_o(of, par, optr)) break;
                }
            }
            if (wq == 3) {
                bar_sync(10 + wg, 128);
                warp_release(&g_flag[F_O + rb64 * 32 + hp]);
                if (elect()) mbar_arrive(BAR(B_D + 8));
                __syncwarp();
            } else {
                bar_arrive(10 + wg, 128);
            }

            if (wg < 2) {
                const int trow = (c >> 4) * 4 + ((c >> 3) & 1) + 2 * wg;
                float acc[56];
                out_gemm(acc, sb, wg);
                if (wg == 0) mbar_wait(BAR(B_LI));
                bar_sync(2 + wg, 128);
                out_store(acc, sb + (3 + 2 * wg) * UNIT + wq * 4096, P.out_ptr, rank * 448 + tcb * 112, trow * 64 + wq * 16);
            }
        }
    }
}

typedef CUresult (*EncodeFn)(CUtensorMap*, CUtensorMapDataType, cuuint32_t, void*, const cuuint64_t*, const cuuint64_t*, const cuuint32_t*,
                             const cuuint32_t*, CUtensorMapInterleave, CUtensorMapSwizzle, CUtensorMapL2promotion, CUtensorMapFloatOOBfill);

void make_map(EncodeFn enc, CUtensorMap* m, void* base, int rank, const cuuint64_t* dims, const cuuint64_t* strides, const cuuint32_t* box) {
    const cuuint32_t es[3] = {1, 1, 1};
    enc(m, CU_TENSOR_MAP_DATA_TYPE_BFLOAT16, rank, base, dims, strides, box, es, CU_TENSOR_MAP_INTERLEAVE_NONE,
        CU_TENSOR_MAP_SWIZZLE_128B, PROMO, CU_TENSOR_MAP_FLOAT_OOB_FILL_NONE);
}

}

extern "C" void kernel_launch(void* const* d_in, const int* in_sizes, int n_in, void* d_out, int out_size) {
    (void)in_sizes; (void)n_in; (void)out_size;
    void* fn = nullptr;
    cudaDriverEntryPointQueryResult qr;
    cudaGetDriverEntryPoint("cuTensorMapEncodeTiled", &fn, cudaEnableDefault, &qr);
    EncodeFn enc = (EncodeFn)fn;
    Params P;
    for (int b = 0; b < 2; b++) {
        { cuuint64_t d[2] = {448, 2048}, s[1] = {896}; cuuint32_t bx[2] = {64, 128}; make_map(enc, &P.x[b], d_in[3 * b], 2, d, s, bx); }
        { cuuint64_t d[3] = {448, 448, 3}, s[2] = {2688, 896}; cuuint32_t bx[3] = {56, 32, 3}; make_map(enc, &P.w[b], d_in[3 * b + 1], 3, d, s, bx); }
        { cuuint64_t d[2] = {448, 448}, s[1] = {896}; cuuint32_t bx[2] = {64, 64}; make_map(enc, &P.wo64[b], d_in[3 * b + 2], 2, d, s, bx); }
        { cuuint64_t d[2] = {448, 448}, s[1] = {896}; cuuint32_t bx[2] = {48, 64}; make_map(enc, &P.wo48[b], d_in[3 * b + 2], 2, d, s, bx); }
    }
    cudaGetSymbolAddress((void**)&P.s, g_scratch);
    P.out_ptr = (uint8_t*)d_out;
    for (int i = 0; i < 2; i++) P.in[i] = (const uint8_t*)d_in[i];
    cudaFuncSetAttribute(fused_kernel, cudaFuncAttributeMaxDynamicSharedMemorySize, SMEM_BYTES);
    fused_kernel<<<NCTA, NTHREADS, SMEM_BYTES>>>(P);
}
```
